```python
import torch

def _softmax(x, axis=-1):
    return torch.softmax(x, dim=axis)
def _gelu(x):
    return torch.nn.functional.gelu(x, approximate="tanh")
def _silu(x):
    return torch.nn.functional.silu(x)
def _sigmoid(x):
    return torch.sigmoid(x)
def _layernorm(x, axis=-1, eps=1e-5):
    m = x.mean(dim=axis, keepdim=True)
    v = x.var(dim=axis, keepdim=True, unbiased=False)
    return (x - m) / torch.sqrt(v + eps)
def _scatter_add(tgt, idx, src, axis=0):
    return tgt.clone().index_add_(axis, idx, src)
def _segment_sum(src, seg, n):
    out = torch.zeros((n,) + src.shape[1:], dtype=src.dtype)
    return out.index_add_(0, seg, src)
def _pad(x, pw):
    flat = tuple(v for pair in reversed(pw) for v in pair)
    return torch.nn.functional.pad(x, flat)

kernel_name = 'concat_heads__gqa_block_cached__gqa_block_cached__near_ridge'

def setup_inputs():

    _w = (lambda a: (lambda t: t.to(torch.bfloat16) if t.is_floating_point() else t)(torch.as_tensor(a)))
    def _A_setup():
        B, Sq, D = 32, 48, 512
        Hq, Hkv, Sk, Dh = 32, 32, 48, 128
        assert Hq % Hkv == 0, (Hq, Hkv)
        return {
            "x": _w((lambda *s: torch.randn(*s, dtype=torch.bfloat16) * 0.8)(B, Sq, D)),
            "k_cache": _w((lambda *s: torch.randn(*s, dtype=torch.bfloat16) * 0.8)(B, Hkv, Sk, Dh)),
            "v_cache": _w((lambda *s: torch.randn(*s, dtype=torch.bfloat16) * 0.05)(B, Hkv, Sk, Dh)),
            "wq": _w((lambda *s: torch.randn(*s, dtype=torch.bfloat16) * 0.8)(D, Hq * Dh) * (D ** -0.5)),
            "wo": _w((lambda *s: torch.randn(*s, dtype=torch.bfloat16) * 0.05)(Hq * Dh, D) * ((Hq * Dh) ** -0.5)),
        }
    _A_in = _A_setup()

    def _B_setup():
        B, Sq, D = 32, 48, 512
        Hq, Hkv, Sk, Dh = 32, 32, 48, 128
        assert Hq % Hkv == 0, (Hq, Hkv)
        return {
            "x": _w((lambda *s: torch.randn(*s, dtype=torch.bfloat16) * 0.8)(B, Sq, D)),
            "k_cache": _w((lambda *s: torch.randn(*s, dtype=torch.bfloat16) * 0.8)(B, Hkv, Sk, Dh)),
            "v_cache": _w((lambda *s: torch.randn(*s, dtype=torch.bfloat16) * 0.05)(B, Hkv, Sk, Dh)),
            "wq": _w((lambda *s: torch.randn(*s, dtype=torch.bfloat16) * 0.8)(D, Hq * Dh) * (D ** -0.5)),
            "wo": _w((lambda *s: torch.randn(*s, dtype=torch.bfloat16) * 0.05)(Hq * Dh, D) * ((Hq * Dh) ** -0.5)),
        }
    _B_in = _B_setup()

    return {
        "A_x": _A_in["x"],
        "A_k_cache": _A_in["k_cache"],
        "A_v_cache": _A_in["v_cache"],
        "A_wq": _A_in["wq"],
        "A_wo": _A_in["wo"],
        "B_x": _B_in["x"],
        "B_k_cache": _B_in["k_cache"],
        "B_v_cache": _B_in["v_cache"],
        "B_wq": _B_in["wq"],
        "B_wo": _B_in["wo"],
    }

def reference(A_x, A_k_cache, A_v_cache, A_wq, A_wo, B_x, B_k_cache, B_v_cache, B_wq, B_wo):
    def _A_ref(x, k_cache, v_cache, wq, wo):
        B, Sq, D = x.shape
        Hq, Dh = 32, 128
        Hkv = k_cache.shape[1]
        rep = Hq // Hkv
        q = (lambda x, *d: x.permute(*d))((x @ wq).reshape(B, Sq, Hq, Dh), 0, 2, 1, 3)
        k = (lambda x, n, axis: torch.repeat_interleave(x, n, dim=axis))(k_cache, rep, axis=1)
        v = (lambda x, n, axis: torch.repeat_interleave(x, n, dim=axis))(v_cache, rep, axis=1)
        scores = torch.einsum("bhqd,bhkd->bhqk", q, k) * (Dh ** -0.5)
        p = _softmax(scores, axis=-1)
        o = torch.einsum("bhqk,bhkd->bhqd", p, v)
        return (lambda x, *d: x.permute(*d))(o, 0, 2, 1, 3).reshape(B, Sq, Hq * Dh) @ wo

    def _B_ref(x, k_cache, v_cache, wq, wo):
        B, Sq, D = x.shape
        Hq, Dh = 32, 128
        Hkv = k_cache.shape[1]
        rep = Hq // Hkv
        q = (lambda x, *d: x.permute(*d))((x @ wq).reshape(B, Sq, Hq, Dh), 0, 2, 1, 3)
        k = (lambda x, n, axis: torch.repeat_interleave(x, n, dim=axis))(k_cache, rep, axis=1)
        v = (lambda x, n, axis: torch.repeat_interleave(x, n, dim=axis))(v_cache, rep, axis=1)
        scores = torch.einsum("bhqd,bhkd->bhqk", q, k) * (Dh ** -0.5)
        p = _softmax(scores, axis=-1)
        o = torch.einsum("bhqk,bhkd->bhqd", p, v)
        return (lambda x, *d: x.permute(*d))(o, 0, 2, 1, 3).reshape(B, Sq, Hq * Dh) @ wo

    a = _A_ref(A_x, A_k_cache, A_v_cache, A_wq, A_wo)
    b = _B_ref(B_x, B_k_cache, B_v_cache, B_wq, B_wo)
    return torch.concatenate([a, b], axis=-1)
```

```cpp
#include <cuda_runtime.h>
#include <cuda_bf16.h>
#include <cuda.h>
#include <stdint.h>

namespace {

constexpr int ROWS = 1536;
constexpr int DM   = 512;
constexpr int NH   = 32;
constexpr int DH   = 128;
constexpr int HD   = 4096;
constexpr int SLOT = 57344;
constexpr int NSLOT = 4;
constexpr int SMEM_BYTES = SLOT * NSLOT + 1024;
constexpr int NTHREADS = 512;

struct Params {
    CUtensorMap x[2], wq[2], k[2], v[2], wo[2], o;
};

__device__ __align__(1024) __nv_bfloat16 g_o[2 * ROWS * HD];
__device__ __align__(1024) float4 g_part[128 * 8 * 384];
__device__ unsigned g_oflag[2 * 8 * 32];
__device__ unsigned g_pflag[128 * 12];
__device__ unsigned g_done;

__device__ __forceinline__ uint32_t smem_u32(const void* p) { return (uint32_t)__cvta_generic_to_shared(p); }
__device__ __forceinline__ void mbar_init(uint32_t a, uint32_t c) { asm volatile("mbarrier.init.shared::cta.b64 [%0], %1;" ::"r"(a), "r"(c)); }
__device__ __forceinline__ void mbar_expect_tx(uint32_t a, uint32_t b) {
    asm volatile("mbarrier.arrive.expect_tx.shared::cta.b64 _, [%0], %1;" ::"r"(a), "r"(b) : "memory");
}
__device__ __forceinline__ void mbar_arrive(uint32_t a) {
    asm volatile("mbarrier.arrive.shared::cta.b64 _, [%0];" ::"r"(a) : "memory");
}
__device__ __forceinline__ void mbar_arrive_cluster(uint32_t a, uint32_t cta) {
    asm volatile("{\n.reg .b32 r;\nmapa.shared::cluster.u32 r, %0, %1;\nmbarrier.arrive.shared::cluster.b64 _, [r];\n}" ::"r"(a), "r"(cta) : "memory");
}
__device__ __forceinline__ bool mbar_try_wait(uint32_t a, uint32_t ph) {
    uint32_t ok;
    asm volatile("{\n.reg .pred p;\nmbarrier.try_wait.parity.shared::cta.b64 p, [%1], %2;\nselp.u32 %0, 1, 0, p;\n}" : "=r"(ok) : "r"(a), "r"(ph) : "memory");
    return ok != 0;
}
__device__ __forceinline__ void mbar_wait(uint32_t a, uint32_t ph) {
    uint32_t n = 0;
    while (!mbar_try_wait(a, ph)) {
        if (++n > (1u << 20)) break;
    }
}
__device__ __forceinline__ void cluster_arrive() { asm volatile("barrier.cluster.arrive.release.aligned;" ::: "memory"); }
__device__ __forceinline__ void cluster_wait() { asm volatile("barrier.cluster.wait.acquire.aligned;" ::: "memory"); }

__device__ __forceinline__ void tma2(uint32_t dst, const CUtensorMap* m, int c0, int c1, uint32_t bar) {
    asm volatile("cp.async.bulk.tensor.2d.shared::cluster.global.mbarrier::complete_tx::bytes [%0], [%1, {%3, %4}], [%2];"
                 ::"r"(dst), "l"(m), "r"(bar), "r"(c0), "r"(c1) : "memory");
}
__device__ __forceinline__ void tma2_mc(uint32_t dst, const CUtensorMap* m, int c0, int c1, uint32_t bar, uint16_t mask) {
    asm volatile("cp.async.bulk.tensor.2d.shared::cluster.global.mbarrier::complete_tx::bytes.multicast::cluster [%0], [%1, {%3, %4}], [%2], %5;"
                 ::"r"(dst), "l"(m), "r"(bar), "r"(c0), "r"(c1), "h"(mask) : "memory");
}
__device__ __forceinline__ void tma3(uint32_t dst, const CUtensorMap* m, int c0, int c1, int c2, uint32_t bar) {
    asm volatile("cp.async.bulk.tensor.3d.shared::cluster.global.mbarrier::complete_tx::bytes [%0], [%1, {%3, %4, %5}], [%2];"
                 ::"r"(dst), "l"(m), "r"(bar), "r"(c0), "r"(c1), "r"(c2) : "memory");
}
__device__ __forceinline__ void tma3_mc(uint32_t dst, const CUtensorMap* m, int c0, int c1, int c2, uint32_t bar, uint16_t mask) {
    asm volatile("cp.async.bulk.tensor.3d.shared::cluster.global.mbarrier::complete_tx::bytes.multicast::cluster [%0], [%1, {%3, %4, %5}], [%2], %6;"
                 ::"r"(dst), "l"(m), "r"(bar), "r"(c0), "r"(c1), "r"(c2), "h"(mask) : "memory");
}
__device__ __forceinline__ void tma5(uint32_t dst, const CUtensorMap* m, int c0, int c1, int c2, int c3, int c4, uint32_t bar) {
    asm volatile("cp.async.bulk.tensor.5d.shared::cluster.global.mbarrier::complete_tx::bytes [%0], [%1, {%3, %4, %5, %6, %7}], [%2];"
                 ::"r"(dst), "l"(m), "r"(bar), "r"(c0), "r"(c1), "r"(c2), "r"(c3), "r"(c4) : "memory");
}
__device__ __forceinline__ void tma5_prefetch(const CUtensorMap* m, int c0, int c1, int c2, int c3, int c4) {
    asm volatile("cp.async.bulk.prefetch.tensor.5d.L2.global [%0, {%1, %2, %3, %4, %5}];"
                 ::"l"(m), "r"(c0), "r"(c1), "r"(c2), "r"(c3), "r"(c4) : "memory");
}
__device__ __forceinline__ void tma3_prefetch(const CUtensorMap* m, int c0, int c1, int c2) {
    asm volatile("cp.async.bulk.prefetch.tensor.3d.L2.global [%0, {%1, %2, %3}];"
                 ::"l"(m), "r"(c0), "r"(c1), "r"(c2) : "memory");
}
__device__ __forceinline__ void prefetch_tmap(const CUtensorMap* m) {
    asm volatile("prefetch.tensormap [%0];" ::"l"(m) : "memory");
}

__device__ __forceinline__ uint64_t make_desc(uint32_t addr, uint32_t lbo, uint32_t sbo) {
    uint64_t d = 0;
    d |= (uint64_t)((addr & 0x3FFFF) >> 4);
    d |= (uint64_t)((lbo >> 4) & 0x3FFF) << 16;
    d |= (uint64_t)((sbo >> 4) & 0x3FFF) << 32;
    d |= (uint64_t)1 << 62;
    return d;
}
#define WG_FENCE() asm volatile("wgmma.fence.sync.aligned;" ::: "memory")
#define WG_COMMIT() asm volatile("wgmma.commit_group.sync.aligned;" ::: "memory")
#define WG_WAIT(n) asm volatile("wgmma.wait_group.sync.aligned %0;" ::"n"(n) : "memory")

#define R8(a, i) "+f"(a[i]), "+f"(a[i + 1]), "+f"(a[i + 2]), "+f"(a[i + 3]), "+f"(a[i + 4]), "+f"(a[i + 5]), "+f"(a[i + 6]), "+f"(a[i + 7])
#define R16(a, i) R8(a, i), R8(a, i + 8)
#define R48(a) R16(a, 0), R16(a, 16), R16(a, 32)
#define R64(a) R16(a, 0), R16(a, 16), R16(a, 32), R16(a, 48)
#define L48 "%0,%1,%2,%3,%4,%5,%6,%7,%8,%9,%10,%11,%12,%13,%14,%15,%16,%17,%18,%19,%20,%21,%22,%23,%24,%25,%26,%27,%28,%29,%30,%31,%32,%33,%34,%35,%36,%37,%38,%39,%40,%41,%42,%43,%44,%45,%46,%47"
#define L64 L48 ",%48,%49,%50,%51,%52,%53,%54,%55,%56,%57,%58,%59,%60,%61,%62,%63"

__device__ __forceinline__ void wgmma_n128_ss_tb(float (&d)[64], uint64_t da, uint64_t db, int acc) {
    asm volatile("{\n.reg .pred p;\nsetp.ne.b32 p, %66, 0;\n"
                 "wgmma.mma_async.sync.aligned.m64n128k16.f32.bf16.bf16 {" L64 "}, %64, %65, p, 1, 1, 0, 1;\n}"
                 : R64(d) : "l"(da), "l"(db), "r"(acc));
}
__device__ __forceinline__ void wgmma_n128_rs_tb(float (&d)[64], uint32_t a0, uint32_t a1, uint32_t a2, uint32_t a3, uint64_t db, int acc) {
    asm volatile("{\n.reg .pred p;\nsetp.ne.b32 p, %69, 0;\n"
                 "wgmma.mma_async.sync.aligned.m64n128k16.f32.bf16.bf16 {" L64 "}, {%64,%65,%66,%67}, %68, p, 1, 1, 1;\n}"
                 : R64(d) : "r"(a0), "r"(a1), "r"(a2), "r"(a3), "l"(db), "r"(acc));
}
__device__ __forceinline__ void wgmma_n96_rs(float (&d)[48], uint32_t a0, uint32_t a1, uint32_t a2, uint32_t a3, uint64_t db, int acc) {
    asm volatile("{\n.reg .pred p;\nsetp.ne.b32 p, %53, 0;\n"
                 "wgmma.mma_async.sync.aligned.m64n96k16.f32.bf16.bf16 {" L48 "}, {%48,%49,%50,%51}, %52, p, 1, 1, 0;\n}"
                 : R48(d) : "r"(a0), "r"(a1), "r"(a2), "r"(a3), "l"(db), "r"(acc));
}
template <int N>
__device__ __forceinline__ void reg_fence(float (&d)[N]) {
#pragma unroll
    for (int i = 0; i < N; i++) asm volatile("" : "+f"(d[i])::"memory");
}
template <int N>
__device__ __forceinline__ void reg_fence_u(uint32_t (&d)[N]) {
#pragma unroll
    for (int i = 0; i < N; i++) asm volatile("" : "+r"(d[i])::"memory");
}
__device__ __forceinline__ uint32_t pack_bf16(float lo, float hi) {
    uint32_t r;
    asm("cvt.rn.bf16x2.f32 %0, %1, %2;" : "=r"(r) : "f"(hi), "f"(lo));
    return r;
}
__device__ __forceinline__ uint32_t pack_bf16v(float lo, float hi) {
    uint32_t r;
    asm volatile("cvt.rn.bf16x2.f32 %0, %1, %2;" : "=r"(r) : "f"(hi), "f"(lo));
    return r;
}
__device__ __forceinline__ float fast_exp2(float x) {
    float y;
    asm("ex2.approx.ftz.f32 %0, %1;" : "=f"(y) : "f"(x));
    return y;
}
__device__ __forceinline__ float fast_rcp(float x) {
    float y;
    asm("rcp.approx.ftz.f32 %0, %1;" : "=f"(y) : "f"(x));
    return y;
}
__device__ __forceinline__ uint4 quad_transpose(uint32_t v0, uint32_t v1, uint32_t v2, uint32_t v3, int t) {
    const bool odd = t & 1, hi = t & 2;
    uint32_t a = odd ? v0 : v1, b = odd ? v2 : v3;
    uint32_t ra = __shfl_xor_sync(0xffffffffu, a, 1), rb = __shfl_xor_sync(0xffffffffu, b, 1);
    uint32_t kl = odd ? v1 : v0, kh = odd ? v3 : v2;
    uint32_t L0 = odd ? ra : kl, L1 = odd ? kl : ra, H0 = odd ? rb : kh, H1 = odd ? kh : rb;
    uint32_t s0 = hi ? L0 : H0, s1 = hi ? L1 : H1;
    uint32_t r0 = __shfl_xor_sync(0xffffffffu, s0, 2), r1 = __shfl_xor_sync(0xffffffffu, s1, 2);
    uint4 w;
    w.x = hi ? r0 : L0; w.y = hi ? r1 : L1; w.z = hi ? H0 : r0; w.w = hi ? H1 : r1;
    return w;
}
__device__ __forceinline__ unsigned ld_acquire(const unsigned* p) {
    unsigned v;
    asm volatile("ld.acquire.gpu.global.u32 %0, [%1];" : "=r"(v) : "l"(p) : "memory");
    return v;
}

__device__ __forceinline__ void softmax24(float (&s)[24], uint32_t (&p)[12]) {
    const float sc = 0.08838834764831845f * 1.4426950408889634f;
    float m0 = s[0], m1 = s[2];
#pragma unroll
    for (int j = 0; j < 6; j++) {
        m0 = fmaxf(m0, fmaxf(s[4 * j], s[4 * j + 1]));
        m1 = fmaxf(m1, fmaxf(s[4 * j + 2], s[4 * j + 3]));
    }
    m0 = fmaxf(m0, __shfl_xor_sync(0xffffffffu, m0, 1));
    m1 = fmaxf(m1, __shfl_xor_sync(0xffffffffu, m1, 1));
    m0 = fmaxf(m0, __shfl_xor_sync(0xffffffffu, m0, 2));
    m1 = fmaxf(m1, __shfl_xor_sync(0xffffffffu, m1, 2));
    const float b0 = -m0 * sc, b1 = -m1 * sc;
    float l0 = 0.f, l1 = 0.f;
#pragma unroll
    for (int j = 0; j < 6; j++) {
        s[4 * j] = fast_exp2(fmaf(s[4 * j], sc, b0));
        s[4 * j + 1] = fast_exp2(fmaf(s[4 * j + 1], sc, b0));
        s[4 * j + 2] = fast_exp2(fmaf(s[4 * j + 2], sc, b1));
        s[4 * j + 3] = fast_exp2(fmaf(s[4 * j + 3], sc, b1));
        l0 += s[4 * j] + s[4 * j + 1];
        l1 += s[4 * j + 2] + s[4 * j + 3];
    }
    l0 += __shfl_xor_sync(0xffffffffu, l0, 1);
    l1 += __shfl_xor_sync(0xffffffffu, l1, 1);
    l0 += __shfl_xor_sync(0xffffffffu, l0, 2);
    l1 += __shfl_xor_sync(0xffffffffu, l1, 2);
    const float i0 = fast_rcp(l0), i1 = fast_rcp(l1);
#pragma unroll
    for (int j = 0; j < 6; j++) {
        p[2 * j] = pack_bf16(s[4 * j] * i0, s[4 * j + 1] * i0);
        p[2 * j + 1] = pack_bf16(s[4 * j + 2] * i1, s[4 * j + 3] * i1);
    }
}

__global__ void __cluster_dims__(2, 1, 1) __launch_bounds__(NTHREADS, 1)
fused_attn_kernel(const __grid_constant__ Params P, __nv_bfloat16* __restrict__ out) {
    extern __shared__ uint8_t smem_raw[];
    __shared__ __align__(8) uint64_t s_full[NSLOT], s_empty[NSLOT], s_odone[2];
    const uint32_t sbase = (smem_u32(smem_raw) + 1023u) & ~1023u;
    const int tid = threadIdx.x;
    const int warp = tid >> 5, lane = tid & 31;
    const int cta = blockIdx.x;
    const int r = cta & 1, p = cta >> 1;
    const uint32_t full0 = smem_u32(&s_full[0]), empty0 = smem_u32(&s_empty[0]), odone0 = smem_u32(&s_odone[0]);

    const int br = p >> 5;
    const int rg1 = ((p >> 3) & 3) * 2 + r;
    const int q1 = p & 7;
    const int rg2 = (p >> 2) & 7;
    const int kh = (p >> 1) & 1;
    const int cq = (p & 1) * 2 + r;

    if (tid == 0) {
#pragma unroll
        for (int i = 0; i < NSLOT; i++) {
            mbar_init(full0 + 8 * i, 1);
            mbar_init(empty0 + 8 * i, 6);
        }
        mbar_init(odone0, 12);
        mbar_init(odone0 + 8, 12);
        asm volatile("fence.mbarrier_init.release.cluster;" ::: "memory");
    }
    __syncthreads();
    cluster_arrive();
    const unsigned epoch = (*((volatile unsigned*)&g_done)) >> 7;
    cluster_wait();

    if (warp >= 12) {
        asm volatile("setmaxnreg.dec.sync.aligned.u32 24;");
        if (warp == 12 && lane == 0) {
            prefetch_tmap(&P.x[br]); prefetch_tmap(&P.wq[br]); prefetch_tmap(&P.k[br]); prefetch_tmap(&P.v[br]);
            int u = 0;
            for (int t = 0; t < 2; t++) {
                const int hp = (q1 >> 2) * 8 + t * 4 + (q1 & 3);
                for (int ks = 0; ks < 8; ks++, u++) {
                    const int s = u & (NSLOT - 1);
                    mbar_wait(empty0 + 8 * s, ((u / NSLOT) & 1) ^ 1);
                    const uint32_t dst = sbase + s * SLOT;
                    mbar_expect_tx(full0 + 8 * s, SLOT);
                    tma2(dst, &P.x[br], ks * 64, rg1 * 192, full0 + 8 * s);
                    tma3_mc(dst + 24576 + r * 16384, &P.wq[br], 0, ks * 64, (hp * 2 + r) * 2, full0 + 8 * s, 3);
                    if (t == 0 && ks >= 3 && ks < 7) {
                        const int j = ks - 3;
                        tma5_prefetch(j < 2 ? &P.k[br] : &P.v[br], 0, 0, rg1 * 4, 0, hp * 2 + (j & 1));
                    }
                }
                for (int j = 0; j < 4; j++, u++) {
                    const int s = u & (NSLOT - 1);
                    mbar_wait(empty0 + 8 * s, ((u / NSLOT) & 1) ^ 1);
                    mbar_expect_tx(full0 + 8 * s, 49152);
                    tma5(sbase + s * SLOT, j < 2 ? &P.k[br] : &P.v[br], 0, 0, rg1 * 4, 0, hp * 2 + (j & 1), full0 + 8 * s);
                    if (t == 0) {
                        tma5_prefetch(j < 2 ? &P.k[br] : &P.v[br], 0, 0, rg1 * 4, 0, (hp + 4) * 2 + (j & 1));
                    }
                }
            }
            const unsigned target = 12u * (epoch + 1u);
            for (int st = 0; st < 32; st++, u++) {
                const int s = u & (NSLOT - 1);
                mbar_wait(empty0 + 8 * s, ((u / NSLOT) & 1) ^ 1);
                const uint32_t dst = sbase + s * SLOT;
                const int k0 = kh * 2048 + st * 64;
                mbar_expect_tx(full0 + 8 * s, 40960);
                tma3(dst + 24576, &P.wo[br], 0, k0, cq * 2, full0 + 8 * s);
                if ((st & 1) == 0) {
                    const unsigned* f = &g_oflag[(br * 8 + rg2) * 32 + (k0 >> 7)];
                    uint32_t n = 0;
                    while ((int)(ld_acquire(f) - target) < 0) {
                        if (++n > (1u << 20)) break;
                    }
                    asm volatile("fence.proxy.async.global;" ::: "memory");
                }
                tma2_mc(dst + r * 12288, &P.o, k0, br * ROWS + rg2 * 192 + r * 96, full0 + 8 * s, 3);
            }
        } else if (warp == 13 && lane == 0) {
            for (int i = 0; i < 4; i++) {
                const int t = i >> 1;
                const int hp = (q1 >> 2) * 8 + t * 4 + (q1 & 3);
                mbar_wait(odone0 + 8 * (i & 1), t & 1);
                asm volatile("fence.proxy.async.global;" ::: "memory");
                __threadfence();
                atomicAdd(&g_oflag[(br * 8 + rg1) * 32 + hp * 2 + (i & 1)], 12u);
            }
        }
        __syncwarp();
        cluster_arrive();
        cluster_wait();
    } else {
        asm volatile("setmaxnreg.inc.sync.aligned.u32 160;");
        const int wg = warp >> 2;
        const int wl = warp & 3;
        const int g = lane >> 2, t4 = lane & 3;
        const bool signal = (tid & 127) < 2;
        const uint32_t sig_cta = tid & 1;
        const bool is_hi = (wg * 64 + wl * 16) >= (wg + 1) * 48;
        int u = 0;
#define RELEASE(uu) do { if (signal) mbar_arrive_cluster(empty0 + 8 * ((uu) & (NSLOT - 1)), sig_cta); } while (0)
#define WAIT_FULL(uu) mbar_wait(full0 + 8 * ((uu) & (NSLOT - 1)), ((uu) / NSLOT) & 1)

        for (int t = 0; t < 2; t++) {
            const int hp = (q1 >> 2) * 8 + t * 4 + (q1 & 3);
            uint32_t q0[32], q1f[32];
            {
                float a0[64], a1[64];
#pragma unroll
                for (int i = 0; i < 64; i++) { a0[i] = 0.f; a1[i] = 0.f; }
                for (int ks = 0; ks < 8; ks++, u++) {
                    WAIT_FULL(u);
                    const uint32_t sl = sbase + (u & (NSLOT - 1)) * SLOT;
                    const uint64_t da = make_desc(sl + wg * 8192, 16, 1024);
                    const uint64_t db = make_desc(sl + 24576, 8192, 1024);
                    WG_FENCE();
#pragma unroll
                    for (int kk = 0; kk < 4; kk++) {
                        wgmma_n128_ss_tb(a0, da + kk * 2, db + kk * 128, 1);
                        wgmma_n128_ss_tb(a1, da + kk * 2, db + 1024 + kk * 128, 1);
                    }
                    WG_COMMIT();
                    if (ks > 0) {
                        WG_WAIT(1);
                        RELEASE(u - 1);
                    }
                }
                WG_WAIT(0);
                reg_fence(a0);
                reg_fence(a1);
                RELEASE(u - 1);
#pragma unroll
                for (int i = 31; i >= 0; i--) q0[i] = pack_bf16v(a0[2 * i], a0[2 * i + 1]);
#pragma unroll
                for (int i = 31; i >= 0; i--) q1f[i] = pack_bf16v(a1[2 * i], a1[2 * i + 1]);
            }
            float sv0[24], sv1[24];
            uint32_t pf[12];
            uint32_t pa[24];
            float s[48];
            WAIT_FULL(u);
            {
                const uint64_t dk = make_desc(sbase + (u & (NSLOT - 1)) * SLOT + wg * 6144, 16, 1024);
                WG_FENCE();
#pragma unroll
                for (int kk = 0; kk < 8; kk++)
                    wgmma_n96_rs(s, q0[4 * kk], q0[4 * kk + 1], q0[4 * kk + 2], q0[4 * kk + 3],
                                 dk + (kk >> 2) * 1536 + (kk & 3) * 2, kk != 0);
                WG_COMMIT();
                WG_WAIT(0);
                reg_fence(s);
                RELEASE(u);
#pragma unroll
                for (int i = 0; i < 24; i++) sv0[i] = is_hi ? s[24 + i] : s[i];
            }
            WAIT_FULL(u + 1);
            {
                const uint64_t dk = make_desc(sbase + ((u + 1) & (NSLOT - 1)) * SLOT + wg * 6144, 16, 1024);
                WG_FENCE();
#pragma unroll
                for (int kk = 0; kk < 8; kk++)
                    wgmma_n96_rs(s, q1f[4 * kk], q1f[4 * kk + 1], q1f[4 * kk + 2], q1f[4 * kk + 3],
                                 dk + (kk >> 2) * 1536 + (kk & 3) * 2, kk != 0);
                WG_COMMIT();
            }
            softmax24(sv0, pf);
#pragma unroll
            for (int i = 0; i < 12; i++) {
                pa[i] = is_hi ? 0u : pf[i];
                pa[12 + i] = is_hi ? pf[i] : 0u;
            }
            WG_WAIT(0);
            reg_fence(s);
            RELEASE(u + 1);
#pragma unroll
            for (int i = 0; i < 24; i++) sv1[i] = is_hi ? s[24 + i] : s[i];
            float o[64];
            WAIT_FULL(u + 2);
            {
                const uint64_t dv = make_desc(sbase + ((u + 2) & (NSLOT - 1)) * SLOT + wg * 6144, 24576, 1024);
                WG_FENCE();
#pragma unroll
                for (int kk = 0; kk < 6; kk++)
                    wgmma_n128_rs_tb(o, pa[4 * kk], pa[4 * kk + 1], pa[4 * kk + 2], pa[4 * kk + 3], dv + kk * 128, kk != 0);
                WG_COMMIT();
            }
            softmax24(sv1, pf);
            WG_WAIT(0);
            reg_fence(o);
            reg_fence_u(pa);
            RELEASE(u + 2);
            uint32_t ok[32];
#pragma unroll
            for (int i = 0; i < 32; i++) ok[i] = pack_bf16(o[2 * i], o[2 * i + 1]);
#pragma unroll
            for (int i = 0; i < 12; i++) {
                pa[i] = is_hi ? 0u : pf[i];
                pa[12 + i] = is_hi ? pf[i] : 0u;
            }
            WAIT_FULL(u + 3);
            {
                const uint64_t dv = make_desc(sbase + ((u + 3) & (NSLOT - 1)) * SLOT + wg * 6144, 24576, 1024);
                WG_FENCE();
#pragma unroll
                for (int kk = 0; kk < 6; kk++)
                    wgmma_n128_rs_tb(o, pa[4 * kk], pa[4 * kk + 1], pa[4 * kk + 2], pa[4 * kk + 3], dv + kk * 128, kk != 0);
                WG_COMMIT();
            }
            __nv_bfloat16* orow = g_o + (size_t)(br * ROWS + rg1 * 192 + wg * 64 + wl * 16 + g) * HD + hp * 256 + t4 * 8;
#pragma unroll
            for (int G = 0; G < 4; G++) {
                uint4 w0 = quad_transpose(ok[8 * G], ok[8 * G + 2], ok[8 * G + 4], ok[8 * G + 6], t4);
                uint4 w1 = quad_transpose(ok[8 * G + 1], ok[8 * G + 3], ok[8 * G + 5], ok[8 * G + 7], t4);
                *(uint4*)(orow + G * 32) = w0;
                *(uint4*)(orow + 8 * HD + G * 32) = w1;
            }
            __syncwarp();
            if (lane == 0) mbar_arrive(odone0);
            WG_WAIT(0);
            reg_fence(o);
            reg_fence_u(pa);
            RELEASE(u + 3);
#pragma unroll
            for (int i = 0; i < 32; i++) ok[i] = pack_bf16(o[2 * i], o[2 * i + 1]);
#pragma unroll
            for (int G = 0; G < 4; G++) {
                uint4 w0 = quad_transpose(ok[8 * G], ok[8 * G + 2], ok[8 * G + 4], ok[8 * G + 6], t4);
                uint4 w1 = quad_transpose(ok[8 * G + 1], ok[8 * G + 3], ok[8 * G + 5], ok[8 * G + 7], t4);
                *(uint4*)(orow + 128 + G * 32) = w0;
                *(uint4*)(orow + 128 + 8 * HD + G * 32) = w1;
            }
            __syncwarp();
            if (lane == 0) mbar_arrive(odone0 + 8);
            u += 4;
        }

        float acc[64];
#pragma unroll
        for (int i = 0; i < 64; i++) acc[i] = 0.f;
        for (int st = 0; st < 32; st++, u++) {
            WAIT_FULL(u);
            const uint32_t sl = sbase + (u & (NSLOT - 1)) * SLOT;
            const uint64_t da = make_desc(sl + wg * 8192, 16, 1024);
            const uint64_t db = make_desc(sl + 24576, 8192, 1024);
            WG_FENCE();
#pragma unroll
            for (int kk = 0; kk < 4; kk++) wgmma_n128_ss_tb(acc, da + kk * 2, db + kk * 128, 1);
            WG_COMMIT();
            if (st > 0) {
                WG_WAIT(1);
                RELEASE(u - 1);
            }
        }
        WG_WAIT(0);
        reg_fence(acc);
        {
            float4* dstp = g_part + (size_t)cta * 8 * 384 + tid;
#pragma unroll
            for (int j = 0; j < 8; j++) {
                float4 v;
                v.x = kh ? acc[4 * j] : acc[32 + 4 * j];
                v.y = kh ? acc[4 * j + 1] : acc[32 + 4 * j + 1];
                v.z = kh ? acc[4 * j + 2] : acc[32 + 4 * j + 2];
                v.w = kh ? acc[4 * j + 3] : acc[32 + 4 * j + 3];
                __stcg(dstp + j * 384, v);
            }
            __syncwarp();
            const int peer = cta ^ 4;
            if (lane == 0) {
                __threadfence();
                asm volatile("st.relaxed.gpu.global.u32 [%0], %1;" ::"l"(&g_pflag[cta * 12 + warp]), "r"(epoch + 1u) : "memory");
                const unsigned* f = &g_pflag[peer * 12 + warp];
                uint32_t n = 0;
                while (ld_acquire(f) != epoch + 1u) {
                    if (++n > (1u << 20)) break;
                }
            }
            __syncwarp();
            const float4* srcp = g_part + (size_t)peer * 8 * 384 + tid;
            uint32_t ok[16];
#pragma unroll
            for (int j = 0; j < 8; j++) {
                float4 v = __ldcg(srcp + j * 384);
                v.x += kh ? acc[32 + 4 * j] : acc[4 * j];
                v.y += kh ? acc[32 + 4 * j + 1] : acc[4 * j + 1];
                v.z += kh ? acc[32 + 4 * j + 2] : acc[4 * j + 2];
                v.w += kh ? acc[32 + 4 * j + 3] : acc[4 * j + 3];
                ok[2 * j] = pack_bf16(v.x, v.y);
                ok[2 * j + 1] = pack_bf16(v.z, v.w);
            }
            __nv_bfloat16* orow = out + (size_t)(rg2 * 192 + wg * 64 + wl * 16 + g) * 1024 + br * 512 + cq * 128 + kh * 64 + t4 * 8;
#pragma unroll
            for (int G = 0; G < 2; G++) {
                uint4 w0 = quad_transpose(ok[8 * G], ok[8 * G + 2], ok[8 * G + 4], ok[8 * G + 6], t4);
                uint4 w1 = quad_transpose(ok[8 * G + 1], ok[8 * G + 3], ok[8 * G + 5], ok[8 * G + 7], t4);
                *(uint4*)(orow + G * 32) = w0;
                *(uint4*)(orow + 8 * 1024 + G * 32) = w1;
            }
        }
        cluster_arrive();
        cluster_wait();
        if (tid == 0) atomicAdd(&g_done, 1u);
    }
}

typedef CUresult (*EncodeFn)(CUtensorMap*, CUtensorMapDataType, cuuint32_t, void*, const cuuint64_t*, const cuuint64_t*,
                             const cuuint32_t*, const cuuint32_t*, CUtensorMapInterleave, CUtensorMapSwizzle,
                             CUtensorMapL2promotion, CUtensorMapFloatOOBfill);

void encode(EncodeFn fn, CUtensorMap* m, void* ptr, int rank, const cuuint64_t* dims, const cuuint64_t* strides, const cuuint32_t* box) {
    cuuint32_t es[5] = {1, 1, 1, 1, 1};
    fn(m, CU_TENSOR_MAP_DATA_TYPE_BFLOAT16, rank, ptr, dims, strides, box, es, CU_TENSOR_MAP_INTERLEAVE_NONE,
       CU_TENSOR_MAP_SWIZZLE_128B, CU_TENSOR_MAP_L2_PROMOTION_L2_256B, CU_TENSOR_MAP_FLOAT_OOB_FILL_NONE);
}

}

extern "C" void kernel_launch(void* const* d_in, const int* in_sizes, int n_in, void* d_out, int out_size) {
    static EncodeFn fn = nullptr;
    if (!fn) {
        void* f = nullptr;
        cudaDriverEntryPointQueryResult st;
        cudaGetDriverEntryPoint("cuTensorMapEncodeTiled", &f, cudaEnableDefault, &st);
        fn = (EncodeFn)f;
        cudaFuncSetAttribute(fused_attn_kernel, cudaFuncAttributeMaxDynamicSharedMemorySize, SMEM_BYTES);
    }
    Params P;
    for (int b = 0; b < 2; b++) {
        void* x = d_in[b * 5 + 0];
        void* k = d_in[b * 5 + 1];
        void* v = d_in[b * 5 + 2];
        void* wq = d_in[b * 5 + 3];
        void* wo = d_in[b * 5 + 4];
        {
            cuuint64_t dims[2] = {DM, ROWS};
            cuuint64_t str[1] = {DM * 2};
            cuuint32_t box[2] = {64, 192};
            encode(fn, &P.x[b], x, 2, dims, str, box);
        }
        {
            cuuint64_t dims[3] = {64, DM, HD / 64};
            cuuint64_t str[2] = {HD * 2, 128};
            cuuint32_t box[3] = {64, 64, 2};
            encode(fn, &P.wq[b], wq, 3, dims, str, box);
        }
        {
            cuuint64_t dims[5] = {64, 48, 32, 2, NH};
            cuuint64_t str[4] = {DH * 2, (cuuint64_t)NH * 48 * DH * 2, 128, 48 * DH * 2};
            cuuint32_t box[5] = {64, 48, 4, 2, 1};
            encode(fn, &P.k[b], k, 5, dims, str, box);
            encode(fn, &P.v[b], v, 5, dims, str, box);
        }
        {
            cuuint64_t dims[3] = {64, HD, DM / 64};
            cuuint64_t str[2] = {DM * 2, 128};
            cuuint32_t box[3] = {64, 64, 2};
            encode(fn, &P.wo[b], wo, 3, dims, str, box);
        }
    }
    {
        void* optr = nullptr;
        cudaGetSymbolAddress(&optr, g_o);
        cuuint64_t dims[2] = {HD, 2 * ROWS};
        cuuint64_t str[1] = {HD * 2};
        cuuint32_t box[2] = {64, 96};
        encode(fn, &P.o, optr, 2, dims, str, box);
    }
    fused_attn_kernel<<<128, NTHREADS, SMEM_BYTES>>>(P, (__nv_bfloat16*)d_out);
}
```

```cpp
#include <cuda_runtime.h>
#include <cuda_bf16.h>
#include <cuda.h>
#include <stdint.h>

namespace {

constexpr int ROWS = 1536;
constexpr int DM = 512;
constexpr int HD = 4096;
constexpr int NW = 4;
constexpr int NR = 3;
constexpr int PFD = 16;
constexpr int VPF = 2;
constexpr int SCH = 4096;
constexpr int HS = 4;
#define GH(i) ((i) * HS + kq)
constexpr int OFF_X = 0;
constexpr int OFF_RING = 98304;
constexpr int OFF_Q = OFF_RING + 2 * NW * 8192;
constexpr int OFF_KV = OFF_Q + 24576;
constexpr int OFF_P = OFF_KV + 24576;
constexpr int SMEM_USED = OFF_P + 10240;
constexpr int SMEM_BYTES = SMEM_USED + 1024;
constexpr int OFF_V = OFF_X;
constexpr int OFF_P7 = OFF_X + 7 * 12288;
constexpr int NTHREADS = 384;
constexpr int PIMG = 4608;

struct Params {
    CUtensorMap x[2], wq[2], k[2], v[2], wo[2], out, kh[2];
    const uint8_t* xp[2];
    const uint8_t* wqp[2];
};

__device__ __align__(1024) uint8_t g_p[128 * 16 * PIMG];
__device__ __align__(1024) uint4 g_part[128 * 3 * 2 * 6 * 128];
__device__ unsigned g_pflag[128 * 4];
__device__ unsigned g_done;

__device__ __forceinline__ uint32_t smem_u32(const void* p) { return (uint32_t)__cvta_generic_to_shared(p); }
__device__ __forceinline__ void mbar_init(uint32_t a, uint32_t c) { asm volatile("mbarrier.init.shared::cta.b64 [%0], %1;" ::"r"(a), "r"(c)); }
__device__ __forceinline__ void mbar_expect_tx(uint32_t a, uint32_t b) {
    asm volatile("mbarrier.arrive.expect_tx.shared::cta.b64 _, [%0], %1;" ::"r"(a), "r"(b) : "memory");
}
__device__ __forceinline__ void mbar_arrive(uint32_t a) {
    asm volatile("mbarrier.arrive.shared::cta.b64 _, [%0];" ::"r"(a) : "memory");
}
__device__ __forceinline__ void mbar_wait(uint32_t a, uint32_t ph) {
    asm volatile(
        "{\n.reg .pred p;\n.reg .u32 n;\nmov.u32 n, 0;\n"
        "WAIT_%=:\n"
        "mbarrier.try_wait.parity.shared::cta.b64 p, [%0], %1;\n"
        "@p bra DONE_%=;\n"
        "add.u32 n, n, 1;\n"
        "setp.lt.u32 p, n, 200000;\n"
        "@p bra WAIT_%=;\n"
        "DONE_%=:\n}" ::"r"(a), "r"(ph) : "memory");
}
__device__ __forceinline__ void bar_sync(int id, int n) { asm volatile("bar.sync %0, %1;" ::"r"(id), "r"(n) : "memory"); }
__device__ __forceinline__ void fence_async_smem() { asm volatile("fence.proxy.async.shared::cta;" ::: "memory"); }

__device__ __forceinline__ void tma2(uint32_t dst, const CUtensorMap* m, int c0, int c1, uint32_t bar) {
    asm volatile("cp.async.bulk.tensor.2d.shared::cluster.global.mbarrier::complete_tx::bytes [%0], [%1, {%3, %4}], [%2];"
                 ::"r"(dst), "l"(m), "r"(bar), "r"(c0), "r"(c1) : "memory");
}
__device__ __forceinline__ void tma2_mc(uint32_t dst, const CUtensorMap* m, int c0, int c1, uint32_t bar, uint16_t mask) {
    asm volatile("cp.async.bulk.tensor.2d.shared::cluster.global.mbarrier::complete_tx::bytes.multicast::cluster [%0], [%1, {%3, %4}], [%2], %5;"
                 ::"r"(dst), "l"(m), "r"(bar), "r"(c0), "r"(c1), "h"(mask) : "memory");
}
__device__ __forceinline__ void tma2_prefetch(const CUtensorMap* m, int c0, int c1) {
    asm volatile("cp.async.bulk.prefetch.tensor.2d.L2.global [%0, {%1, %2}];" ::"l"(m), "r"(c0), "r"(c1) : "memory");
}
__device__ __forceinline__ void tma3_ef(uint32_t dst, const CUtensorMap* m, int c0, int c1, int c2, uint32_t bar) {
    uint64_t pol;
    asm volatile("createpolicy.fractional.L2::evict_first.b64 %0, 1.0;" : "=l"(pol));
    asm volatile("cp.async.bulk.tensor.3d.shared::cluster.global.mbarrier::complete_tx::bytes.L2::cache_hint [%0], [%1, {%3, %4, %5}], [%2], %6;"
                 ::"r"(dst), "l"(m), "r"(bar), "r"(c0), "r"(c1), "r"(c2), "l"(pol) : "memory");
}
__device__ __forceinline__ void tma3_prefetch(const CUtensorMap* m, int c0, int c1, int c2) {
    asm volatile("cp.async.bulk.prefetch.tensor.3d.L2.global [%0, {%1, %2, %3}];" ::"l"(m), "r"(c0), "r"(c1), "r"(c2) : "memory");
}
__device__ __forceinline__ void bulk_g2s(uint32_t dst, const void* src, uint32_t bytes, uint32_t bar) {
    asm volatile("cp.async.bulk.shared::cluster.global.mbarrier::complete_tx::bytes [%0], [%1], %2, [%3];"
                 ::"r"(dst), "l"(src), "r"(bytes), "r"(bar) : "memory");
}
__device__ __forceinline__ void tma2_store(const CUtensorMap* m, int c0, int c1, uint32_t src) {
    asm volatile("cp.async.bulk.tensor.2d.global.shared::cta.bulk_group [%0, {%2, %3}], [%1];"
                 ::"l"(m), "r"(src), "r"(c0), "r"(c1) : "memory");
}
__device__ __forceinline__ void prefetch_tmap(const CUtensorMap* m) {
    asm volatile("prefetch.tensormap [%0];" ::"l"(m) : "memory");
}

constexpr uint32_t DESC_HI_SW128 = (1024u >> 4) | (1u << 30);
constexpr uint32_t DESC_HI_P = (768u >> 4);
#define WG_COMMIT() asm volatile("wgmma.commit_group.sync.aligned;" ::: "memory")
#define WG_WAIT(n) asm volatile("wgmma.wait_group.sync.aligned %0;" ::"n"(n) : "memory")

#define R8(a, i) "+f"(a[i]), "+f"(a[i + 1]), "+f"(a[i + 2]), "+f"(a[i + 3]), "+f"(a[i + 4]), "+f"(a[i + 5]), "+f"(a[i + 6]), "+f"(a[i + 7])
#define R24(a) R8(a, 0), R8(a, 8), R8(a, 16)
#define R48(a) R24(a), R8(a, 24), R8(a, 32), R8(a, 40)
#define L24 "%0,%1,%2,%3,%4,%5,%6,%7,%8,%9,%10,%11,%12,%13,%14,%15,%16,%17,%18,%19,%20,%21,%22,%23"
#define L48 L24 ",%24,%25,%26,%27,%28,%29,%30,%31,%32,%33,%34,%35,%36,%37,%38,%39,%40,%41,%42,%43,%44,%45,%46,%47"

__device__ __forceinline__ void wgmma_tile_nc(float (&d)[48], uint32_t alo, uint32_t blo, int acc) {
    asm volatile("{\n.reg .pred p;\n.reg .b64 da, db;\n.reg .b32 ta, tb;\n"
                 "setp.ne.b32 p, %50, 0;\n"
                 "wgmma.fence.sync.aligned;\n"
                 "mov.b64 da, {%48, %51};\nmov.b64 db, {%49, %51};\n"
                 "wgmma.mma_async.sync.aligned.m64n96k16.f32.bf16.bf16 {" L48 "}, da, db, p, 1, 1, 1, 0;\n"
                 "add.u32 ta, %48, 128;\nadd.u32 tb, %49, 2;\nmov.b64 da, {ta, %51};\nmov.b64 db, {tb, %51};\n"
                 "wgmma.mma_async.sync.aligned.m64n96k16.f32.bf16.bf16 {" L48 "}, da, db, 1, 1, 1, 1, 0;\n"
                 "add.u32 ta, %48, 256;\nadd.u32 tb, %49, 4;\nmov.b64 da, {ta, %51};\nmov.b64 db, {tb, %51};\n"
                 "wgmma.mma_async.sync.aligned.m64n96k16.f32.bf16.bf16 {" L48 "}, da, db, 1, 1, 1, 1, 0;\n"
                 "add.u32 ta, %48, 384;\nadd.u32 tb, %49, 6;\nmov.b64 da, {ta, %51};\nmov.b64 db, {tb, %51};\n"
                 "wgmma.mma_async.sync.aligned.m64n96k16.f32.bf16.bf16 {" L48 "}, da, db, 1, 1, 1, 1, 0;\n}"
                 : R48(d) : "r"(alo), "r"(blo), "r"(acc), "n"(DESC_HI_SW128) : "memory");
}
__device__ __forceinline__ uint32_t desc_lo(uint32_t addr) { return ((addr & 0x3FFFF) >> 4) | (1u << 16); }
__device__ __forceinline__ bool elect_one() {
    uint32_t p;
    asm volatile("{\n.reg .pred p;\nelect.sync _|p, 0xffffffff;\nselp.u32 %0, 1, 0, p;\n}" : "=r"(p));
    return p != 0;
}
__device__ __forceinline__ void wgmma_s_seq(float (&d)[24], uint32_t qlo, uint32_t klo) {
#define SSTEP(qo, ko, acc)                                                                       \
    "add.u32 ta, %24, " #qo ";\nadd.u32 tb, %25, " #ko ";\nmov.b64 da, {ta, %26};\nmov.b64 db, {tb, %26};\n" \
    "wgmma.mma_async.sync.aligned.m64n48k16.f32.bf16.bf16 {" L24 "}, da, db, " #acc ", 1, 1, 0, 0;\n"
    asm volatile("{\n.reg .b64 da, db;\n.reg .b32 ta, tb;\n"
                 SSTEP(0, 0, 0) SSTEP(2, 2, 1) SSTEP(4, 4, 1) SSTEP(6, 6, 1)
                 SSTEP(768, 384, 1) SSTEP(770, 386, 1) SSTEP(772, 388, 1) SSTEP(774, 390, 1)
                 "}"
                 : R24(d) : "r"(qlo), "r"(klo), "n"(DESC_HI_SW128) : "memory");
#undef SSTEP
}
template <int ACC>
__device__ __forceinline__ void wgmma_s_half(float (&d)[24], uint32_t qlo, uint32_t klo) {
#define SSTEP(qo, ko, acc)                                                                       \
    "add.u32 ta, %24, " #qo ";\nadd.u32 tb, %25, " #ko ";\nmov.b64 da, {ta, %26};\nmov.b64 db, {tb, %26};\n" \
    "wgmma.mma_async.sync.aligned.m64n48k16.f32.bf16.bf16 {" L24 "}, da, db, " acc ", 1, 1, 0, 0;\n"
    asm volatile("{\n.reg .b64 da, db;\n.reg .b32 ta, tb;\n"
                 SSTEP(0, 0, "%27") SSTEP(2, 2, "1") SSTEP(4, 4, "1") SSTEP(6, 6, "1")
                 "}"
                 : R24(d) : "r"(qlo), "r"(klo), "n"(DESC_HI_SW128), "n"(ACC) : "memory");
#undef SSTEP
}
__device__ __forceinline__ void wgmma_pv_seq(float (&d)[24], uint32_t vlo, uint32_t plo) {
#define PSTEP(vo, po, acc)                                                                       \
    "add.u32 ta, %24, " #vo ";\nadd.u32 tb, %25, " #po ";\nmov.b64 da, {ta, %26};\nmov.b64 db, {tb, %27};\n" \
    "wgmma.mma_async.sync.aligned.m64n48k16.f32.bf16.bf16 {" L24 "}, da, db, " #acc ", 1, 1, 1, 0;\n"
    asm volatile("{\n.reg .b64 da, db;\n.reg .b32 ta, tb;\n"
                 "wgmma.fence.sync.aligned;\n"
                 PSTEP(0, 0, 0) PSTEP(128, 16, 1) PSTEP(256, 32, 1)
                 "wgmma.commit_group.sync.aligned;\n}"
                 : R24(d) : "r"(vlo), "r"(plo), "n"(DESC_HI_SW128), "n"(DESC_HI_P) : "memory");
#undef PSTEP
}
template <int N>
__device__ __forceinline__ void reg_fence(float (&d)[N]) {
#pragma unroll
    for (int i = 0; i < N; i++) asm volatile("" : "+f"(d[i])::"memory");
}
__device__ __forceinline__ uint32_t pack_bf16(float lo, float hi) {
    uint32_t r;
    asm("cvt.rn.bf16x2.f32 %0, %1, %2;" : "=r"(r) : "f"(hi), "f"(lo));
    return r;
}
__device__ __forceinline__ float fast_exp2(float x) {
    float y;
    asm("ex2.approx.ftz.f32 %0, %1;" : "=f"(y) : "f"(x));
    return y;
}
__device__ __forceinline__ float fast_rcp(float x) {
    float y;
    asm("rcp.approx.ftz.f32 %0, %1;" : "=f"(y) : "f"(x));
    return y;
}
__device__ __forceinline__ void stsm_x4_t(uint32_t addr, uint32_t r0, uint32_t r1, uint32_t r2, uint32_t r3) {
    asm volatile("stmatrix.sync.aligned.m8n8.x4.trans.shared.b16 [%0], {%1,%2,%3,%4};" ::"r"(addr), "r"(r0), "r"(r1), "r"(r2), "r"(r3) : "memory");
}
__device__ __forceinline__ unsigned ld_relaxed(const unsigned* p) {
    unsigned v;
    asm volatile("ld.relaxed.gpu.global.u32 %0, [%1];" : "=r"(v) : "l"(p) : "memory");
    return v;
}
template <int NACC>
__device__ __forceinline__ void store_tile_t(const float (&a)[NACC], uint32_t base_plus_lane) {
#pragma unroll
    for (int jj = 0; jj < NACC / 8; jj++)
        stsm_x4_t(base_plus_lane + jj * 2048, pack_bf16(a[8 * jj], a[8 * jj + 1]), pack_bf16(a[8 * jj + 2], a[8 * jj + 3]),
                  pack_bf16(a[8 * jj + 4], a[8 * jj + 5]), pack_bf16(a[8 * jj + 6], a[8 * jj + 7]));
}

__device__ __forceinline__ void tile_coords(int u, int kq, int w, int& c0, int& c1) {
    if (u < 64) {
        c0 = GH(u >> 3) * 128 + w * 64;
        c1 = (u & 7) * 64;
    } else {
        const int v = u - 64;
        int head, kb, j;
        if (v < 8) {
            head = 0;
            kb = v & 1; j = v >> 1;
        } else if (v < (8 - NR) * 8) {
            head = v >> 3; kb = (v >> 2) & 1; j = v & 3;
        } else {
            const int vv = v - (8 - NR) * 8;
            j = vv / (2 * NR);
            const int rem = vv - j * (2 * NR);
            head = 8 - NR + (rem >> 1); kb = rem & 1;
        }
        c0 = ((kq + 1 + j) & 3) * 128 + w * 64;
        c1 = GH(head) * 128 + kb * 64;
    }
}
__device__ __forceinline__ uint32_t oslot_off(int s) {
    return s == 0 ? 24576u : (s == 1 ? 49152u : (s == 2 ? (uint32_t)OFF_Q : (uint32_t)OFF_KV));
}

__device__ __forceinline__ uint32_t xbuf_off(int j) { return j == 0 ? 24576u : (j == 1 ? (uint32_t)OFF_V : (uint32_t)(OFF_X + 6 * 12288)); }

struct Bars {
    uint64_t wfull[2][NW], xfull[8], kvfull[2], gfull[3], p7full, qfull, sent[3], ofull[4], fin[2], oempty[4], xfree[3], qempty, hand, wempty[2][NW];
};
constexpr int NBARS = sizeof(Bars) / 8;
static_assert(NBARS <= 2 * NW + 10 + 32, "barrier init covers 18 + 32 barriers");
#define BAR(field) (bars + (uint32_t)offsetof(Bars, field))
#define BIDX(field) ((int)(offsetof(Bars, field) / 8))
__device__ __forceinline__ int oslot_of(int i) { return i & 3; }
__device__ __forceinline__ int ouse_of(int i) { return i >> 2; }

__device__ __forceinline__ bool mbar_test(uint32_t a, uint32_t ph) {
    uint32_t ok;
    asm volatile("{\n.reg .pred p;\nmbarrier.test_wait.parity.shared::cta.b64 p, [%1], %2;\nselp.u32 %0, 1, 0, p;\n}" : "=r"(ok) : "r"(a), "r"(ph) : "memory");
    return ok != 0;
}

extern "C" __global__ void __cluster_dims__(2, 1, 1) __launch_bounds__(NTHREADS, 1)
fused_attn_kernel(const __grid_constant__ Params P) {
    extern __shared__ uint8_t smem_raw[];
    __shared__ __align__(8) Bars s_bars;
    __shared__ uint32_t s_coord[128];
    const uint32_t sbase = (smem_u32(smem_raw) + 1023u) & ~1023u;
    const uint32_t bars = smem_u32(&s_bars);
    const int tid = threadIdx.x;
    const int warp = __shfl_sync(0xffffffffu, tid >> 5, 0), lane = tid & 31;
    int cta;
    {
        const int p = blockIdx.x >> 1, t = p - 4;
        int grp, mem;
        if (p < 4) { grp = 15; mem = p; }
        else if (t < 32) { grp = t & 7; mem = t >> 3; }
        else { mem = (t - 32) / 7; grp = 8 + (t - 32) - mem * 7; }
        cta = (grp * 4 + mem) * 2 + (blockIdx.x & 1);
    }
    const int r = cta & 1, kq = (cta >> 1) & 3, rg = (cta >> 3) & 7, br = cta >> 6;
    const int row0 = rg * 192 + r * 96;
    const int kvrow0 = ((rg * 4 + r * 2) * 32 + GH(0)) * 48;

    if (warp == 8) {
        if (lane < BIDX(gfull)) {
            mbar_init(bars + 8 * lane, 1);
            mbar_expect_tx(bars + 8 * lane, lane < 2 * NW ? 8192 : 12288);
            asm volatile("fence.mbarrier_init.release.cluster;" ::: "memory");
        }
        __syncwarp();
        if (elect_one()) {
#pragma unroll 1
            for (int j = 0; j < 8; j++) {
                tma2(sbase + OFF_X + j * 12288, &P.x[br], j * 64, row0, BAR(xfull) + 8 * j);
                if (j < NW) {
                    tma2(sbase + OFF_RING + j * 8192, &P.wq[br], GH(0) * 128, j * 64, BAR(wfull) + 8 * j);
                    tma2(sbase + OFF_RING + (NW + j) * 8192, &P.wq[br], GH(0) * 128 + 64, j * 64, BAR(wfull) + 8 * (NW + j));
                }
            }
        }
        __syncwarp();
    } else if (warp == 9) {
        asm volatile("cp.async.bulk.prefetch.L2.global [%0], %1;" ::"l"(P.wqp[br] + (size_t)(lane * 16 + rg * 2 + r) * 8192 + GH(0) * 256), "r"(256) : "memory");
        if (lane < 6) asm volatile("cp.async.bulk.prefetch.L2.global [%0], %1;" ::"l"(P.xp[br] + (size_t)row0 * 1024 + (kq * 6 + lane) * 4096), "r"(4096) : "memory");
    } else if (warp == 10) {
        const int b = BIDX(gfull) + lane;
        if (b < NBARS) {
            mbar_init(bars + 8 * b, b >= BIDX(oempty) ? 2 : (b >= BIDX(ofull) ? 4 : (b >= BIDX(qfull) ? 8 : (b == BIDX(p7full) ? 6 : 1))));
            asm volatile("fence.mbarrier_init.release.cluster;" ::: "memory");
        }
    } else if (warp >= 4 && warp < 8) {
        int c0, c1;
        tile_coords(tid - 128, kq, 0, c0, c1);
        s_coord[tid - 128] = (uint32_t)c0 | ((uint32_t)c1 << 16);
    }

    const int wl = warp & 3;
    const uint32_t st_lane = (uint32_t)(((lane & 7) + 8 * (lane >> 4)) * 128 + (((2 * wl + ((lane >> 3) & 1)) ^ (lane & 7)) * 16));

    uint8_t* const pscr = g_p + (size_t)cta * 16 * PIMG;
    constexpr int U0 = 59 + NW - 1;

    if (warp >= 8) {
        const bool ghost = (wl == 3);
        asm volatile("setmaxnreg.dec.sync.aligned.u32 56;");
        bar_sync(0, NTHREADS);
        asm volatile("barrier.cluster.arrive.relaxed.aligned;" ::: "memory");
        auto load_p = [&](int i, int b) {
            mbar_expect_tx(BAR(xfull) + 8 * b, i < 7 ? 12288 + PIMG : 12288);
            if (i < 7) bulk_g2s(sbase + OFF_P + b * PIMG, pscr + (i * 2 + b) * PIMG, PIMG, BAR(xfull) + 8 * b);
        };
        auto load_v = [&](int i, int b) {
            tma3_ef(sbase + OFF_V + b * 12288, &P.v[br], 0, kvrow0 + b * 32 * 48 + i * 48 * HS, 0, BAR(xfull) + 8 * b);
        };
        if (ghost && elect_one()) {
            tma3_ef(sbase + OFF_KV, &P.k[br], 0, kvrow0, 0, BAR(kvfull));
            tma3_ef(sbase + OFF_KV + 12288, &P.k[br], 0, kvrow0 + 32 * 48, 0, BAR(kvfull) + 8);
        }
        __syncwarp();
        asm volatile("barrier.cluster.wait.aligned;" ::: "memory");
        mbar_wait(BAR(xfull), 0);
        mbar_wait(BAR(xfull) + 8, 0);
        if (wl < 2) {
            const int w = wl;
            const uint32_t ring = sbase + OFF_RING + w * (NW * 8192);
            const int pf_pos = rg * 2 + r;
#pragma unroll 1
            for (int un = NW + (r ^ w); un < U0; un += 2) {
                const int sl = un & 3;
                const int up = (un & ~1) + PFD - NW + (pf_pos & 1);
                if (((up ^ pf_pos) & 15) == 0) {
                    const uint32_t c2 = s_coord[up];
                    if (elect_one()) tma2_prefetch(up < 64 ? &P.wq[br] : &P.wo[br], (c2 & 0xffff) + w * 64, c2 >> 16);
                }
                mbar_wait(BAR(wempty) + w * (NW * 8) + 8 * sl, ((un >> 2) - 1) & 1);
                if (elect_one()) {
                    mbar_expect_tx(BAR(wfull) + w * (NW * 8) + 8 * sl, 8192);
                    tma2_mc(ring + sl * 8192, &P.wq[br], GH(un >> 3) * 128 + w * 64, (un & 7) * 64, BAR(wfull) + w * (NW * 8) + 8 * sl, 3);
                }
            }
        } else if (wl == 2) {
            if (elect_one()) {
                prefetch_tmap(&P.wo[br]);
                prefetch_tmap(&P.v[br]);
#pragma unroll 1
                for (int up = 8 + ((rg * 2 + r - 8) & 15); up < PFD; up += 16) {
                    tma2_prefetch(&P.wq[br], GH(up >> 3) * 128, (up & 7) * 64);
                    tma2_prefetch(&P.wq[br], GH(up >> 3) * 128 + 64, (up & 7) * 64);
                }
            }
        } else {
            if (elect_one()) {
#pragma unroll 1
                for (int i = 0; i < 6; i++) {
                    mbar_wait(BAR(qfull), i & 1);
                    if (i >= 6 - 2 * VPF) {
                        const int n = i - (6 - 2 * VPF);
                        tma3_prefetch(&P.v[br], 0, kvrow0 + (n & 1) * 32 * 48 + (n >> 1) * 48 * HS, 0);
                    }
                }
                asm volatile("fence.proxy.async.global;" ::: "memory");
                load_p(0, 0);
                load_p(0, 1);
                mbar_wait(BAR(xfree), 0);
                load_v(0, 0);
                load_v(0, 1);
            }
        }
        __syncwarp();
        const uint32_t v_lo = desc_lo(sbase + OFF_V);
        float s[24];
#pragma unroll
        for (int j = 0; j < 24; j++) s[j] = 0.f;
        uint32_t sp[12];
#pragma unroll 1
        for (int i = 0; i < 8; i++) {
            const int sl = oslot_of(i);
            const uint32_t obase = sbase + oslot_off(sl) + st_lane;
            const uint32_t pb = sbase + (i < 7 ? OFF_P : OFF_P7);
            const uint32_t p_lo = ((pb & 0x3FFFF) >> 4) | (8u << 16);
            if (i == 3 && ghost) {
                mbar_wait(BAR(p7full), 0);
                if (elect_one()) asm volatile("fence.proxy.async.global;" ::: "memory");
                __syncwarp();
            }
            if (i == 7) mbar_wait(BAR(p7full), 0);
            mbar_wait(BAR(xfull), (i + 1) & 1);
            wgmma_pv_seq(s, v_lo, p_lo);
            if (i < 2) mbar_wait(BAR(xfree) + 8 * (i + 1), 0);
            else if (i == 2) mbar_wait(BAR(qempty), 1);
            else if (i >= 4) mbar_wait(BAR(oempty) + 8 * sl, 0);
#pragma unroll
            for (int q = 0; q < 4; q++) {
                const int b = q >> 1, m = q & 1;
                if (q == 1) mbar_wait(BAR(xfull) + 8, (i + 1) & 1);
                WG_WAIT(0);
                reg_fence(s);
#pragma unroll
                for (int j = 0; j < 12; j++) sp[j] = pack_bf16(s[2 * j], s[2 * j + 1]);
#pragma unroll
                for (int j = 0; j < 12; j++) asm volatile("" : "+r"(sp[j])::"memory");
                if (q < 3) wgmma_pv_seq(s, v_lo + (q + 1) * 384, p_lo + ((q + 1) >> 1) * (PIMG / 16));
#pragma unroll
                for (int jj = 0; jj < 3; jj++)
                    stsm_x4_t(obase + m * 12288 + b * 6144 + jj * 2048, sp[4 * jj], sp[4 * jj + 1], sp[4 * jj + 2], sp[4 * jj + 3]);
                if (q == 3) {
                    fence_async_smem();
                    __syncwarp();
                    if (lane == 0) mbar_arrive(BAR(ofull) + 8 * sl);
                }
                if (m == 1 && i < 7 && ghost) {
                    if (elect_one()) { load_p(i + 1, b); load_v(i + 1, b); }
                    __syncwarp();
                }
            }
        }
        asm volatile("barrier.cluster.arrive.relaxed.aligned;" ::: "memory");
        if (wl < 3 && elect_one()) {
            const int j = wl;
            const unsigned tag = ((*((volatile unsigned*)&g_done)) >> 7) + 1u;
            const uint32_t buf = sbase + xbuf_off(j);
            mbar_wait(BAR(sent) + 8 * j, 0);
#pragma unroll 1
            for (int c = 0; c < 24576 / SCH; c++) {
                asm volatile("cp.async.bulk.global.shared::cta.bulk_group [%0], [%1], %2;" ::"l"(g_part + ((size_t)cta * 3 + j) * 1536 + c * (SCH / 16)), "r"(buf + c * SCH), "r"(SCH) : "memory");
                asm volatile("cp.async.bulk.commit_group;" ::: "memory");
                asm volatile("cp.async.bulk.wait_group.read 0;" ::: "memory");
            }
            asm volatile("cp.async.bulk.wait_group 0;" ::: "memory");
            asm volatile("st.release.gpu.global.u32 [%0], %1;" ::"l"(&g_pflag[cta * 4 + j]), "r"(tag) : "memory");
            const int pc = (cta & ~6) | (((kq - 1 - j) & 3) << 1);
            uint32_t n = 0;
            while (ld_relaxed(&g_pflag[pc * 4 + j]) != tag) {
                if (++n > (1u << 22)) break;
                if (j < 2) __nanosleep(300);
            }
            asm volatile("fence.proxy.async.global;" ::: "memory");
            mbar_expect_tx(BAR(gfull) + 8 * j, 24576);
            bulk_g2s(buf, g_part + ((size_t)pc * 3 + j) * 1536, 24576, BAR(gfull) + 8 * j);
        }
        if (ghost) {
            mbar_wait(BAR(hand), 0);
#pragma unroll 1
            for (int un = 113; un < 128; un++) {
                const uint32_t bo = ((r ^ un) & 1) * (NW * 8) + 8 * (un & 3);
                const uint32_t cc = s_coord[un];
                mbar_wait(BAR(wempty) + bo, ((un >> 2) - 1) & 1);
                if (elect_one()) {
                    mbar_expect_tx(BAR(wfull) + bo, 8192);
                    tma2_mc(sbase + OFF_RING + bo * 1024, &P.wo[br], (cc & 0xffff) + ((r ^ un) & 1) * 64, cc >> 16, BAR(wfull) + bo, 3);
                }
                __syncwarp();
            }
        }
        if (ghost && elect_one()) {
            prefetch_tmap(&P.out);
#pragma unroll 1
            for (int w = 0; w < 2; w++) {
                mbar_wait(BAR(fin) + 8 * w, 0);
                tma2_store(&P.out, br * 512 + kq * 128 + w * 64, row0, sbase + OFF_RING + w * (NW * 8192));
                asm volatile("cp.async.bulk.commit_group;" ::: "memory");
            }
            atomicAdd(&g_done, 1u);
            asm volatile("cp.async.bulk.wait_group.read 0;" ::: "memory");
        }
        __syncwarp();
        asm volatile("barrier.cluster.wait.aligned;" ::: "memory");
    } else {
        asm volatile("setmaxnreg.inc.sync.aligned.u32 224;");
        const int w = warp >> 2;
        const bool ctl = (tid & 127) == 0;
        const uint32_t ring = sbase + OFF_RING + w * (NW * 8192);
        const uint32_t wfull = BAR(wfull) + w * (NW * 8);
        float a0[48], a1[48], a2[48], a3[48];
#pragma unroll
        for (int i = 0; i < 48; i++) { a2[i] = 0.f; a3[i] = 0.f; }
        int ub = 0;
        const uint32_t wempty = BAR(wempty) + w * (NW * 8);
        uint32_t rel_addr;
        asm volatile("mapa.shared::cluster.u32 %0, %1, %2;" : "=r"(rel_addr) : "r"(wempty), "r"(r ^ 1));
        const uint32_t ring_lo = desc_lo(ring);
        const int rw = r ^ w;
        const bool role = (wl == 3);
        const bool own_e = role && rw == 0, own_o = role && rw == 1;
        const bool pf_w = (wl == 2);
        const int pf_pos = rg * 2 + r;
        uint32_t nxt = 0;
        bar_sync(0, NTHREADS);
        asm volatile("barrier.cluster.arrive.relaxed.aligned;" ::: "memory");
        asm volatile("barrier.cluster.wait.aligned;" ::: "memory");

#define TILEX(ACC, baddr, first, p, DED, EXTRA, SLICE)                                            \
    do {                                                                                          \
        if (!nxt) mbar_wait(wfull + 8 * ((p) & 3), ((p) >> 2) & 1);                               \
        wgmma_tile_nc(ACC, ring_lo + ((p) & 3) * 512, desc_lo(baddr), (first) ? 0 : 1);           \
        EXTRA;                                                                                    \
        WG_COMMIT();                                                                              \
        nxt = mbar_test(wfull + 8 * (((p) + 1) & 3), (((p) + 1) >> 2) & 1);                       \
        if (!(DED) && (p) == 3 && pf_w) prefetch_w();                                             \
        SLICE;                                                                                    \
        WG_WAIT(1);                                                                               \
        if (((p) & 1) ? own_o : own_e) release(((p) + 3) & 3, (p), DED);                          \
        if (((p) & 1) ? own_e : own_o) produce(((p) + 3) & 3, (p), DED);                          \
    } while (0)
#define TILE(ACC, baddr, first, p) TILEX(ACC, baddr, first, p, false, , )

        auto produce = [&](int ps, int p, bool ded) {
            const int un = ub + p + 3;
            if (ded) {
                if (un >= NW && un < 128 && elect_one()) mbar_arrive(wempty + 8 * ps);
            } else if (un < 128) {
                const uint32_t cc = s_coord[un];
                mbar_wait(wempty + 8 * ps, (((p + 7) & 7) >> 2) & 1);
                if (elect_one()) {
                    mbar_expect_tx(wfull + 8 * ps, 8192);
                    tma2_mc(ring + ps * 8192, un < 64 ? &P.wq[br] : &P.wo[br], (cc & 0xffff) + w * 64, cc >> 16, wfull + 8 * ps, 3);
                }
            }
        };
        auto release = [&](int ps, int p, bool ded) {
            const int un = ub + p + 3;
            if (un >= NW && un < 128 && elect_one()) {
                if (ded) asm volatile("mbarrier.arrive.shared::cluster.b64 _, [%0];" ::"r"(rel_addr + 8 * ps) : "memory");
                else asm volatile("mbarrier.arrive.shared::cluster.b64 _, [%0], 2;" ::"r"(rel_addr + 8 * ps) : "memory");
                mbar_expect_tx(wfull + 8 * ps, 8192);
            }
        };
        auto prefetch_w = [&]() {
            const int up = ub + PFD + (pf_pos & 7);
            if ((up & 15) == pf_pos && up < 128) {
                const uint32_t cc = s_coord[up];
                if (elect_one()) tma2_prefetch(up < 64 ? &P.wq[br] : &P.wo[br], (cc & 0xffff) + w * 64, cc >> 16);
            }
        };
        const uint32_t qst = sbase + OFF_Q + w * 12288 + st_lane;
        auto drain_q = [&](float (&a)[48], int i, int half) {
            if (half == 0) {
                reg_fence(a);
                if (i > 0) mbar_wait(BAR(qempty), (i - 1) & 1);
            }
#pragma unroll
            for (int jj = 0; jj < 3; jj++) {
                const int q = half * 3 + jj;
                stsm_x4_t(qst + q * 2048, pack_bf16(a[8 * q], a[8 * q + 1]), pack_bf16(a[8 * q + 2], a[8 * q + 3]),
                          pack_bf16(a[8 * q + 4], a[8 * q + 5]), pack_bf16(a[8 * q + 6], a[8 * q + 7]));
            }
        };
        auto drain_done = [&]() {
            fence_async_smem();
            __syncwarp();
            if (lane == 0) mbar_arrive(BAR(qfull));
        };
        float e0[24], e1[24];
#pragma unroll
        for (int j = 0; j < 24; j++) { e0[j] = 0.f; e1[j] = 0.f; }
        float b0 = 0.f, b1 = 0.f;
        const float sc = 0.08838834764831845f * 1.4426950408889634f;
        const uint32_t q_lo = desc_lo(sbase + OFF_Q) + w * 384, k_lo = desc_lo(sbase + OFF_KV) + w * 768;
        auto s_wait = [&](int i) {
            mbar_wait(BAR(kvfull) + 8 * w, i & 1);
            mbar_wait(BAR(qfull), i & 1);
        };
        auto k_half0 = [&](int i) {
            if (role) {
                if (elect_one()) {
                    mbar_expect_tx(BAR(kvfull) + 8 * w, 12288);
                    tma3_ef(sbase + OFF_KV + w * 12288, &P.kh[br], 0, kvrow0 + w * 32 * 48 + (i + 1) * 48 * HS, 0, BAR(kvfull) + 8 * w);
                }
                __syncwarp();
            }
        };
        auto sm_a = [&](float (&e)[24], int i) {
            reg_fence(e);
            if (role) {
                if (elect_one()) {
                    mbar_arrive(BAR(qempty));
                    if (i < 7) tma3_ef(sbase + OFF_KV + w * 12288 + 6144, &P.kh[br], 0, kvrow0 + w * 32 * 48 + (i + 1) * 48 * HS, 1, BAR(kvfull) + 8 * w);
                }
                __syncwarp();
            } else {
                float m0 = fmaxf(e[0], e[1]), m1 = fmaxf(e[2], e[3]);
#pragma unroll
                for (int j = 1; j < 6; j++) {
                    m0 = fmaxf(m0, fmaxf(e[4 * j], e[4 * j + 1]));
                    m1 = fmaxf(m1, fmaxf(e[4 * j + 2], e[4 * j + 3]));
                }
                m0 = fmaxf(m0, __shfl_xor_sync(0xffffffffu, m0, 1));
                m1 = fmaxf(m1, __shfl_xor_sync(0xffffffffu, m1, 1));
                m0 = fmaxf(m0, __shfl_xor_sync(0xffffffffu, m0, 2));
                m1 = fmaxf(m1, __shfl_xor_sync(0xffffffffu, m1, 2));
                b0 = -m0 * sc;
                b1 = -m1 * sc;
            }
            asm volatile("" : "+f"(b0), "+f"(b1)::"memory");
        };
        auto sm_b = [&](float (&e)[24], int j0, int j1) {
            if (!role) {
#pragma unroll
                for (int j = j0; j < j1; j++) {
                    e[4 * j] = fast_exp2(fmaf(e[4 * j], sc, b0));
                    e[4 * j + 1] = fast_exp2(fmaf(e[4 * j + 1], sc, b0));
                    e[4 * j + 2] = fast_exp2(fmaf(e[4 * j + 2], sc, b1));
                    e[4 * j + 3] = fast_exp2(fmaf(e[4 * j + 3], sc, b1));
                }
            }
            reg_fence(e);
        };
        auto sm_c = [&](float (&e)[24]) {
            if (!role) {
                float l0 = (e[0] + e[1]) + (e[4] + e[5]) + ((e[8] + e[9]) + (e[12] + e[13])) + ((e[16] + e[17]) + (e[20] + e[21]));
                float l1 = (e[2] + e[3]) + (e[6] + e[7]) + ((e[10] + e[11]) + (e[14] + e[15])) + ((e[18] + e[19]) + (e[22] + e[23]));
                l0 += __shfl_xor_sync(0xffffffffu, l0, 1);
                l1 += __shfl_xor_sync(0xffffffffu, l1, 1);
                l0 += __shfl_xor_sync(0xffffffffu, l0, 2);
                l1 += __shfl_xor_sync(0xffffffffu, l1, 2);
                b0 = fast_rcp(l0);
                b1 = fast_rcp(l1);
            }
            asm volatile("" : "+f"(b0), "+f"(b1)::"memory");
        };
        auto sm_d = [&](float (&e)[24], int i) {
            if (!role) {
                if (i < 7) {
                    uint32_t* pp = (uint32_t*)(pscr + (i * 2 + w) * PIMG + wl * 1536) + lane;
#pragma unroll
                    for (int j = 0; j < 6; j++) {
                        pp[j * 32] = pack_bf16(e[4 * j] * b0, e[4 * j + 1] * b0);
                        pp[192 + j * 32] = pack_bf16(e[4 * j + 2] * b1, e[4 * j + 3] * b1);
                    }
                } else {
                    const uint32_t pa = sbase + OFF_P7 + w * PIMG + wl * 1536 + lane * 4;
#pragma unroll
                    for (int j = 0; j < 6; j++) {
                        asm volatile("st.shared.b32 [%0], %1;" ::"r"(pa + j * 128), "r"(pack_bf16(e[4 * j] * b0, e[4 * j + 1] * b0)) : "memory");
                        asm volatile("st.shared.b32 [%0], %1;" ::"r"(pa + 768 + j * 128), "r"(pack_bf16(e[4 * j + 2] * b1, e[4 * j + 3] * b1)) : "memory");
                    }
                    fence_async_smem();
                    __syncwarp();
                    if (lane == 0) mbar_arrive(BAR(p7full));
                }
            }
        };

        const uint32_t xb = sbase + OFF_X;
#define REST(ACC, H0, SMP, SMC, EP, EC, i, DED, LAST)                                             \
    if (H0) mbar_wait(BAR(xfull) + 24, 0);                                                        \
    TILEX(ACC, xb + 3 * 12288, false, 3, DED, , if (SMP) sm_b(EP, 3, 6));                         \
    if (H0) mbar_wait(BAR(xfull) + 32, 0);                                                        \
    if (SMC) s_wait(i);                                                                           \
    TILEX(ACC, xb + 4 * 12288, false, 4, DED, if (SMC) wgmma_s_half<0>(EC, q_lo, k_lo), if (SMP) sm_c(EP)); \
    if (LAST && ctl) mbar_arrive(BAR(xfree) + 8);                                                 \
    if (H0) mbar_wait(BAR(xfull) + 40, 0);                                                        \
    TILEX(ACC, xb + 5 * 12288, false, 5, DED, if (SMC) wgmma_s_half<1>(EC, q_lo + 768, k_lo + 384), if (SMP) sm_d(EP, (i) - 1)); \
    if (H0) mbar_wait(BAR(xfull) + 48, 0);                                                        \
    TILEX(ACC, xb + 6 * 12288, false, 6, DED, , if (SMC) k_half0(i));                             \
    if (H0) mbar_wait(BAR(xfull) + 56, 0);                                                        \
    TILEX(ACC, xb + 7 * 12288, false, 7, DED, , if (SMC) sm_a(EC, i));                            \
    ub += 8;
#define START(ACC, PREV, i, SMP, EP)                                                              \
    TILEX(ACC, xb, true, 0, true, , if (SMP) sm_b(EP, 0, 3));                                     \
    TILEX(ACC, xb + 12288, false, 1, true, , drain_q(PREV, i, 0); drain_q(PREV, i, 1));           \
    TILEX(ACC, xb + 2 * 12288, false, 2, true, , drain_done());
        mbar_wait(BAR(xfull), 0);
        TILEX(a2, xb, true, 0, true, , );
        mbar_wait(BAR(xfull) + 8, 0);
        TILEX(a2, xb + 12288, false, 1, true, , );
        mbar_wait(BAR(xfull) + 16, 0);
        TILEX(a2, xb + 2 * 12288, false, 2, true, , );
        REST(a2, true, false, false, e1, e0, 0, true, false)
        START(a3, a2, 0, false, e1)
#pragma unroll 1
        for (int hp = 0; hp < 3; hp++) {
            REST(a3, false, hp > 0, true, e1, e0, 2 * hp, true, false)
            START(a2, a3, 2 * hp + 1, true, e0)
            REST(a2, false, true, true, e0, e1, 2 * hp + 1, true, false)
            START(a3, a2, 2 * hp + 2, true, e1)
        }
        if (ctl) mbar_arrive(BAR(xfree));
        s_wait(6);
        TILEX(a3, xb + 3 * 12288, false, 3, false, wgmma_s_half<0>(e0, q_lo, k_lo), sm_b(e1, 3, 6));
        TILEX(a3, xb + 4 * 12288, false, 4, false, wgmma_s_half<1>(e0, q_lo + 768, k_lo + 384), sm_c(e1));
        if (ctl) mbar_arrive(BAR(xfree) + 8);
        TILEX(a3, xb + 5 * 12288, false, 5, false, , k_half0(6); sm_d(e1, 5));
        TILEX(a3, xb + 6 * 12288, false, 6, false, , sm_a(e0, 6));
        TILEX(a3, xb + 7 * 12288, false, 7, false, , sm_b(e0, 0, 4));
        if (ctl) mbar_arrive(BAR(xfree) + 16);
        ub += 8;

        {
            mbar_wait(BAR(ofull), 0);
            const uint32_t ob = sbase + oslot_off(0);
#pragma unroll
            for (int j = 0; j < 48; j++) a0[j] = 0.f;
            TILEX(a0, ob, true, 0, false, , sm_b(e0, 4, 6); sm_c(e0));
            TILEX(a0, ob + 12288, false, 1, false, , drain_q(a3, 7, 0); drain_q(a3, 7, 1); drain_done(); sm_d(e0, 6));
#pragma unroll
            for (int j = 0; j < 48; j++) a1[j] = 0.f;
#pragma unroll
            for (int j = 0; j < 24; j++) e1[j] = 0.f;
            s_wait(7);
            TILEX(a1, ob, true, 2, false, wgmma_s_seq(e1, q_lo, k_lo), );
            TILE(a1, ob + 12288, false, 3);
#pragma unroll
            for (int j = 0; j < 48; j++) a2[j] = 0.f;
            TILEX(a2, ob, false, 4, false, , sm_a(e1, 7); sm_b(e1, 0, 3));
            TILEX(a2, ob + 12288, false, 5, false, , sm_b(e1, 3, 6); sm_c(e1); sm_d(e1, 7));
#pragma unroll
            for (int j = 0; j < 48; j++) a3[j] = 0.f;
            TILE(a3, ob, false, 6);
            TILE(a3, ob + 12288, false, 7);
            ub += 8;
        }
#pragma unroll 1
        for (int i = 1; i < 8 - NR; i++) {
            const int sl = oslot_of(i);
            mbar_wait(BAR(ofull) + 8 * sl, ouse_of(i) & 1);
            const uint32_t ob = sbase + oslot_off(sl);
            TILE(a0, ob, false, 0);
            if (ctl) mbar_arrive(BAR(oempty) + 8 * oslot_of(i - 1));
            TILE(a1, ob, false, 1);
            TILE(a2, ob, false, 2);
            TILE(a3, ob, false, 3);
            TILE(a0, ob + 12288, false, 4);
            TILE(a1, ob + 12288, false, 5);
            TILE(a2, ob + 12288, false, 6);
            TILE(a3, ob + 12288, false, 7);
            ub += 8;
        }
        const uint32_t xlane = w * 12288 + (tid & 127) * 16;
        auto send = [&](float (&a)[48], int j) {
            reg_fence(a);
#pragma unroll
            for (int q = 0; q < 6; q++)
                asm volatile("st.shared.v4.b32 [%0], {%1,%2,%3,%4};" ::"r"(sbase + xbuf_off(j) + xlane + q * 2048),
                             "r"(pack_bf16(a[8 * q], a[8 * q + 1])), "r"(pack_bf16(a[8 * q + 2], a[8 * q + 3])),
                             "r"(pack_bf16(a[8 * q + 4], a[8 * q + 5])), "r"(pack_bf16(a[8 * q + 6], a[8 * q + 7])) : "memory");
            fence_async_smem();
            __syncwarp();
            if (lane == 0) mbar_arrive(BAR(sent) + 8 * j);
        };
        auto gather = [&](float (&a)[48], int j) {
            mbar_wait(BAR(gfull) + 8 * j, 0);
#pragma unroll
            for (int q = 0; q < 6; q++) {
                uint4 v;
                asm volatile("ld.shared.v4.b32 {%0,%1,%2,%3}, [%4];" : "=r"(v.x), "=r"(v.y), "=r"(v.z), "=r"(v.w) : "r"(sbase + xbuf_off(j) + xlane + q * 2048) : "memory");
                a[8 * q] += __uint_as_float(v.x << 16);
                a[8 * q + 1] += __uint_as_float(v.x & 0xffff0000u);
                a[8 * q + 2] += __uint_as_float(v.y << 16);
                a[8 * q + 3] += __uint_as_float(v.y & 0xffff0000u);
                a[8 * q + 4] += __uint_as_float(v.z << 16);
                a[8 * q + 5] += __uint_as_float(v.z & 0xffff0000u);
                a[8 * q + 6] += __uint_as_float(v.w << 16);
                a[8 * q + 7] += __uint_as_float(v.w & 0xffff0000u);
            }
        };
        static_assert(NR == 3, "window code is written for NR == 3");
        const uint32_t o5 = sbase + oslot_off(1), o6 = sbase + oslot_off(2), o7 = sbase + oslot_off(3);
#define WINDOW(ACC, FIRSTSEG, p0, AFTER_FIRST)                                                    \
    if (FIRSTSEG) mbar_wait(BAR(ofull) + 8, 1);                                                   \
    TILEX(ACC, o5, false, p0, !(FIRSTSEG), , );                                                   \
    AFTER_FIRST;                                                                                  \
    TILEX(ACC, o5 + 12288, false, p0 + 1, !(FIRSTSEG), , );                                       \
    if (FIRSTSEG) mbar_wait(BAR(ofull) + 16, 1);                                                  \
    TILEX(ACC, o6, false, p0 + 2, !(FIRSTSEG), , );                                               \
    TILEX(ACC, o6 + 12288, false, p0 + 3, !(FIRSTSEG), , );                                       \
    if (FIRSTSEG) mbar_wait(BAR(ofull) + 24, 1);                                                  \
    TILEX(ACC, o7, false, p0 + 4, !(FIRSTSEG), , );                                               \
    TILEX(ACC, o7 + 12288, false, p0 + 5, !(FIRSTSEG), , );
        WINDOW(a0, true, 0, if (ctl) mbar_arrive(BAR(oempty)))
        if (role && elect_one()) mbar_arrive(BAR(hand));
        __syncwarp();
        WINDOW(a1, false, 6, mbar_wait(BAR(oempty), 1); send(a0, 0))
        WINDOW(a2, false, 12, send(a1, 1))
        WINDOW(a3, false, 18, send(a2, 2))
        WG_WAIT(0);
        reg_fence(a3);
        asm volatile("barrier.cluster.arrive.relaxed.aligned;" ::: "memory");
#pragma unroll 1
        for (int j = 0; j < 3; j++) {
            gather(a3, j);
            store_tile_t(a3, ring + st_lane);
            fence_async_smem();
            __syncwarp();
        }
        if (lane == 0) mbar_arrive(BAR(fin) + 8 * w);
        __syncwarp();
        asm volatile("barrier.cluster.wait.aligned;" ::: "memory");
    }
}


typedef CUresult (*EncodeFn)(CUtensorMap*, CUtensorMapDataType, cuuint32_t, void*, const cuuint64_t*, const cuuint64_t*,
                             const cuuint32_t*, const cuuint32_t*, CUtensorMapInterleave, CUtensorMapSwizzle,
                             CUtensorMapL2promotion, CUtensorMapFloatOOBfill);

void encode(EncodeFn fn, CUtensorMap* m, void* ptr, int rank, const cuuint64_t* dims, const cuuint64_t* strides, const cuuint32_t* box) {
    cuuint32_t es[5] = {1, 1, 1, 1, 1};
    fn(m, CU_TENSOR_MAP_DATA_TYPE_BFLOAT16, rank, ptr, dims, strides, box, es, CU_TENSOR_MAP_INTERLEAVE_NONE,
       CU_TENSOR_MAP_SWIZZLE_128B, CU_TENSOR_MAP_L2_PROMOTION_L2_128B, CU_TENSOR_MAP_FLOAT_OOB_FILL_NONE);
}

}

extern "C" void kernel_launch(void* const* d_in, const int* in_sizes, int n_in, void* d_out, int out_size) {
    static EncodeFn fn = nullptr;
    if (!fn) {
        void* f = nullptr;
        cudaDriverEntryPointQueryResult st;
        cudaGetDriverEntryPoint("cuTensorMapEncodeTiled", &f, cudaEnableDefault, &st);
        fn = (EncodeFn)f;
        cudaFuncSetAttribute(fused_attn_kernel, cudaFuncAttributeMaxDynamicSharedMemorySize, SMEM_BYTES);
    }
    Params P;
    for (int b = 0; b < 2; b++) {
        void* x = d_in[b * 5 + 0];
        void* k = d_in[b * 5 + 1];
        void* v = d_in[b * 5 + 2];
        void* wq = d_in[b * 5 + 3];
        void* wo = d_in[b * 5 + 4];
        P.xp[b] = (const uint8_t*)x;
        P.wqp[b] = (const uint8_t*)wq;
        {
            cuuint64_t dims[2] = {DM, ROWS};
            cuuint64_t str[1] = {DM * 2};
            cuuint32_t box[2] = {64, 96};
            encode(fn, &P.x[b], x, 2, dims, str, box);
        }
        {
            cuuint64_t dims[2] = {HD, DM};
            cuuint64_t str[1] = {HD * 2};
            cuuint32_t box[2] = {64, 64};
            encode(fn, &P.wq[b], wq, 2, dims, str, box);
        }
        {
            cuuint64_t dims[3] = {64, 32 * 32 * 48, 2};
            cuuint64_t str[2] = {256, 128};
            cuuint32_t box[3] = {64, 48, 2};
            encode(fn, &P.k[b], k, 3, dims, str, box);
            encode(fn, &P.v[b], v, 3, dims, str, box);
            cuuint32_t boxh[3] = {64, 48, 1};
            encode(fn, &P.kh[b], k, 3, dims, str, boxh);
        }
        {
            cuuint64_t dims[2] = {DM, HD};
            cuuint64_t str[1] = {DM * 2};
            cuuint32_t box[2] = {64, 64};
            encode(fn, &P.wo[b], wo, 2, dims, str, box);
        }
    }
    {
        cuuint64_t dims[2] = {1024, ROWS};
        cuuint64_t str[1] = {2048};
        cuuint32_t box[2] = {64, 96};
        encode(fn, &P.out, d_out, 2, dims, str, box);
    }
    fused_attn_kernel<<<128, NTHREADS, SMEM_BYTES>>>(P);
}
```
